```python
import torch

def _softmax(x, axis=-1):
    return torch.softmax(x, dim=axis)
def _gelu(x):
    return torch.nn.functional.gelu(x, approximate="tanh")
def _silu(x):
    return torch.nn.functional.silu(x)
def _sigmoid(x):
    return torch.sigmoid(x)
def _layernorm(x, axis=-1, eps=1e-5):
    m = x.mean(dim=axis, keepdim=True)
    v = x.var(dim=axis, keepdim=True, unbiased=False)
    return (x - m) / torch.sqrt(v + eps)
def _scatter_add(tgt, idx, src, axis=0):
    return tgt.clone().index_add_(axis, idx, src)
def _segment_sum(src, seg, n):
    out = torch.zeros((n,) + src.shape[1:], dtype=src.dtype)
    return out.index_add_(0, seg, src)
def _pad(x, pw):
    flat = tuple(v for pair in reversed(pw) for v in pair)
    return torch.nn.functional.pad(x, flat)

kernel_name = 'standalone__mha_block_cached__sampling'

def setup_inputs():

    _w = (lambda a: (lambda t: t.to(torch.bfloat16) if t.is_floating_point() else t)(torch.as_tensor(a)))
    B, Sq, D = 16, 1, 1024
    H, Sk, Dh = 32, 2048, 128
    return {
        "x": _w((lambda *s: torch.randn(*s, dtype=torch.bfloat16) * 0.8)(B, Sq, D)),
        "k_cache": _w((lambda *s: torch.randn(*s, dtype=torch.bfloat16) * 0.8)(B, H, Sk, Dh)),
        "v_cache": _w((lambda *s: torch.randn(*s, dtype=torch.bfloat16) * 0.05)(B, H, Sk, Dh)),
        "wq": _w((lambda *s: torch.randn(*s, dtype=torch.bfloat16) * 0.8)(D, H * Dh) * (D ** -0.5)),
        "wo": _w((lambda *s: torch.randn(*s, dtype=torch.bfloat16) * 0.05)(H * Dh, D) * ((H * Dh) ** -0.5)),
    }

def reference(x, k_cache, v_cache, wq, wo):
    B, Sq, D = x.shape
    H, Dh = 32, 128
    q = (lambda x, *d: x.permute(*d))((x @ wq).reshape(B, Sq, H, Dh), 0, 2, 1, 3)
    scores = torch.einsum("bhqd,bhkd->bhqk", q, k_cache) * (Dh ** -0.5)
    p = _softmax(scores, axis=-1)
    o = torch.einsum("bhqk,bhkd->bhqd", p, v_cache)
    return (lambda x, *d: x.permute(*d))(o, 0, 2, 1, 3).reshape(B, Sq, H * Dh) @ wo
```

```cpp
#include <cuda_runtime.h>
#include <cuda.h>
#include <cuda_bf16.h>
#include <stdint.h>

namespace {

#define MHA_SLOTS 8
#define MHA_WIN 3
#define MHA_W0 100
#define MHA_P1 480
#define MHA_DRY 1

constexpr int kB = 16, kD = 1024, kH = 32, kSk = 2048, kDh = 128;
constexpr int kHD = kH * kDh;
constexpr int kPairs = kB * kH;
constexpr int kBigPairs = MHA_P1;
constexpr int kBigChunks = kBigPairs * 16;
constexpr int kChunks = kBigChunks + (kPairs - kBigPairs) * 32;
constexpr int kLastRec = (kB - 1) * kH * 16;
constexpr int kTileBytes = 16384;
constexpr int kSlots = MHA_SLOTS;
constexpr int kWin = MHA_WIN;
constexpr int kWin0 = MHA_W0;
#define MHA_WA 6
#define MHA_WB 6
#define MHA_WC 6
#define MHA_R1 44
#define MHA_R2 88
#define MHA_R3 132
#define MHA_FULLPOLL 8
#define LDREC ld_relaxed_v4
#define LDML ld_relaxed_v4
#define MHA_WWO 2
#define MHA_WWO0 2
#define MHA_SLOTS_MRG 8
#define MHA_EARLY 0
#define MHA_RWO 400
#define LDOUT ld_relaxed_v4
constexpr int kMaxWin = 6;
constexpr int kCW = 8;
constexpr int kThreads = (kCW + 2) * 32;
constexpr int kOwners = 128;
constexpr int kOPitch = 272;
constexpr int kPartStride = 72;
constexpr unsigned kEmpty = 0xffffffffu;
static_assert(kBigPairs >= (kB - 1) * kH && kBigPairs <= kPairs, "only the last batch row is split finer");

constexpr int kOffRing = 0;
constexpr int kOffW = kSlots * kTileBytes;
constexpr int kOffX = kOffW + 65536;
constexpr int kOffO = kOffX;
constexpr int kOffRed = kOffX + 8192;
constexpr int kOffRow = kOffX + 12288;
constexpr int kOffMrg = kOffX + 16384;
constexpr int kOffBar = kOffX + 32768;
constexpr int kBarFull = 0, kBarInfo = kCW * 4, kBarEmpty = kBarInfo + kCW, kBarO = kBarEmpty + kSlots,
              kBarO15 = kBarO + 1, kBarMrg = kBarO15 + 1, kBarLL = kBarMrg + 1, kBarWq = kBarLL + 1, kBarWo = kBarWq + 1, kNumBars = kBarWo + 4;
constexpr int kOffDesc = kOffBar + kNumBars * 8;
constexpr int kSmemBytes = kOffDesc + 2 * kCW * 8 + 16;
static_assert(kSmemBytes <= 232448, "shared memory budget");

constexpr unsigned kPollLimit = 1u << 23;

__device__ unsigned g_epoch;
__device__ unsigned g_work;
__device__ unsigned g_cleared;
__device__ unsigned g_paircnt[kPairs * 8];
__device__ __align__(128) unsigned long long g_q[kB * kHD / 2];
__device__ __align__(128) unsigned g_part[kChunks * kPartStride];
__device__ __align__(128) uint4 g_ll[kOwners * 32 * 32];
__device__ __align__(128) unsigned g_ll15[kOwners * 32 * 8];

#define TS(i) do {} while (0)
#define CK_(i) do {} while (0)

__device__ __forceinline__ uint32_t smem_u32(const void* p) { return (uint32_t)__cvta_generic_to_shared(p); }
__device__ __forceinline__ void mbar_init(uint32_t bar, uint32_t cnt) {
    asm volatile("mbarrier.init.shared::cta.b64 [%0], %1;" ::"r"(bar), "r"(cnt) : "memory");
}
__device__ __forceinline__ void mbar_expect_tx(uint32_t bar, uint32_t bytes) {
    asm volatile("mbarrier.arrive.expect_tx.shared::cta.b64 _, [%0], %1;" ::"r"(bar), "r"(bytes) : "memory");
}
__device__ __forceinline__ void mbar_arrive(uint32_t bar) {
    asm volatile("mbarrier.arrive.shared::cta.b64 _, [%0];" ::"r"(bar) : "memory");
}
__device__ __forceinline__ void mbar_wait(uint32_t bar, uint32_t parity) {
    asm volatile("{\n.reg .pred p;\n.reg .u32 n;\nmov.u32 n, 0;\n"
                 "WAIT_LOOP:\nmbarrier.try_wait.parity.shared::cta.b64 p, [%0], %1;\n@p bra WAIT_DONE;\n"
                 "add.u32 n, n, 1;\nsetp.lt.u32 p, n, 0x400000;\n@p bra WAIT_LOOP;\ntrap;\nWAIT_DONE:\n}\n"
                 ::"r"(bar), "r"(parity) : "memory");
}
__device__ __forceinline__ bool mbar_test(uint32_t bar, uint32_t parity) {
    uint32_t ok;
    asm volatile("{\n.reg .pred p;\nmbarrier.test_wait.parity.shared::cta.b64 p, [%1], %2;\nselp.u32 %0, 1, 0, p;\n}\n"
                 : "=r"(ok) : "r"(bar), "r"(parity) : "memory");
    return ok != 0;
}
__device__ __forceinline__ void poll_tick(unsigned& n) {
    if (++n > kPollLimit) __trap();
}
__device__ __forceinline__ void cp_async16(uint32_t dst, const void* src) {
    asm volatile("cp.async.cg.shared.global.L2::128B [%0], [%1], 16;" ::"r"(dst), "l"(src) : "memory");
}
__device__ __forceinline__ void bulk_load(uint32_t dst, const void* src, uint32_t bytes, uint32_t bar, uint64_t pol) {
    asm volatile("cp.async.bulk.shared::cluster.global.mbarrier::complete_tx::bytes.L2::cache_hint [%0], [%1], %2, [%3], %4;"
                 ::"r"(dst), "l"(src), "r"(bytes), "r"(bar), "l"(pol) : "memory");
}
__device__ __forceinline__ void ldsm_x4(uint32_t& r0, uint32_t& r1, uint32_t& r2, uint32_t& r3, uint32_t addr) {
    asm volatile("ldmatrix.sync.aligned.m8n8.x4.shared.b16 {%0,%1,%2,%3}, [%4];"
                 : "=r"(r0), "=r"(r1), "=r"(r2), "=r"(r3) : "r"(addr) : "memory");
}
__device__ __forceinline__ void ldsm_x4_t(uint32_t& r0, uint32_t& r1, uint32_t& r2, uint32_t& r3, uint32_t addr) {
    asm volatile("ldmatrix.sync.aligned.m8n8.x4.trans.shared.b16 {%0,%1,%2,%3}, [%4];"
                 : "=r"(r0), "=r"(r1), "=r"(r2), "=r"(r3) : "r"(addr) : "memory");
}
__device__ __forceinline__ void mma_bf16(float (&c)[4], uint32_t a0, uint32_t a1, uint32_t a2, uint32_t a3,
                                         uint32_t b0, uint32_t b1) {
    asm volatile("mma.sync.aligned.m16n8k16.row.col.f32.bf16.bf16.f32 {%0,%1,%2,%3}, {%4,%5,%6,%7}, {%8,%9}, {%0,%1,%2,%3};"
                 : "+f"(c[0]), "+f"(c[1]), "+f"(c[2]), "+f"(c[3])
                 : "r"(a0), "r"(a1), "r"(a2), "r"(a3), "r"(b0), "r"(b1));
}
__device__ __forceinline__ uint32_t pack_bf16(float lo, float hi) {
    uint32_t r;
    asm("cvt.rn.bf16x2.f32 %0, %1, %2;" : "=r"(r) : "f"(hi), "f"(lo));
    return r;
}
__device__ __forceinline__ float ex2(float x) {
    float r;
    asm("ex2.approx.ftz.f32 %0, %1;" : "=f"(r) : "f"(x));
    return r;
}
__device__ __forceinline__ float rcp(float x) {
    float r;
    asm("rcp.approx.ftz.f32 %0, %1;" : "=f"(r) : "f"(x));
    return r;
}
__device__ __forceinline__ unsigned ld_relaxed(const unsigned* p) {
    unsigned v;
    asm volatile("ld.relaxed.gpu.global.u32 %0, [%1];" : "=r"(v) : "l"(p) : "memory");
    return v;
}
__device__ __forceinline__ unsigned long long ld_relaxed_u64(const unsigned long long* p) {
    unsigned long long v;
    asm volatile("ld.relaxed.gpu.global.b64 %0, [%1];" : "=l"(v) : "l"(p) : "memory");
    return v;
}
__device__ __forceinline__ void st_relaxed_u64(unsigned long long* p, unsigned long long v) {
    asm volatile("st.relaxed.gpu.global.b64 [%0], %1;" ::"l"(p), "l"(v) : "memory");
}
__device__ __forceinline__ uint2 ld_relaxed_v2(const void* p) {
    uint2 v;
    asm volatile("ld.relaxed.gpu.global.v2.u32 {%0,%1}, [%2];" : "=r"(v.x), "=r"(v.y) : "l"(p) : "memory");
    return v;
}
__device__ __forceinline__ void st_relaxed_v2(void* p, uint2 v) {
    asm volatile("st.relaxed.gpu.global.v2.u32 [%0], {%1,%2};" ::"l"(p), "r"(v.x), "r"(v.y) : "memory");
}
__device__ __forceinline__ void st_relaxed(unsigned* p, unsigned v) {
    asm volatile("st.relaxed.gpu.global.u32 [%0], %1;" ::"l"(p), "r"(v) : "memory");
}
__device__ __forceinline__ unsigned ld_acquire(const unsigned* p) {
    unsigned v;
    asm volatile("ld.acquire.gpu.global.u32 %0, [%1];" : "=r"(v) : "l"(p) : "memory");
    return v;
}
__device__ __forceinline__ void red_release_add(unsigned* p, unsigned v) {
    asm volatile("red.release.gpu.global.add.u32 [%0], %1;" ::"l"(p), "r"(v) : "memory");
}
__device__ __forceinline__ uint4 ld_relaxed_v4(const void* p) {
    uint4 v;
    asm volatile("ld.relaxed.gpu.global.v4.u32 {%0,%1,%2,%3}, [%4];" : "=r"(v.x), "=r"(v.y), "=r"(v.z), "=r"(v.w) : "l"(p) : "memory");
    return v;
}
__device__ __forceinline__ uint4 ld_coherent_v4(const void* p) {
    unsigned long long lo, hi;
    asm volatile("{\n.reg .b128 c, r;\nmov.b128 c, {%3, %3};\natom.relaxed.gpu.global.cas.b128 r, [%2], c, c;\nmov.b128 {%0, %1}, r;\n}\n"
                 : "=l"(lo), "=l"(hi) : "l"(p), "l"(~0ull) : "memory");
    return make_uint4((unsigned)lo, (unsigned)(lo >> 32), (unsigned)hi, (unsigned)(hi >> 32));
}
__device__ __forceinline__ void st_relaxed_v4(void* p, uint4 v) {
    asm volatile("st.relaxed.gpu.global.v4.u32 [%0], {%1,%2,%3,%4};" ::"l"(p), "r"(v.x), "r"(v.y), "r"(v.z), "r"(v.w) : "memory");
}
__device__ __forceinline__ unsigned payload(unsigned u) { return u == kEmpty ? 0x7fffffffu : u; }
__device__ __forceinline__ unsigned payload(float f) { return payload(__float_as_uint(f)); }
__device__ __forceinline__ bool written(const uint4& v) {
    return (v.x != kEmpty) & (v.y != kEmpty) & (v.z != kEmpty) & (v.w != kEmpty);
}
__device__ __forceinline__ void named_bar_sync(int id, int n) {
    asm volatile("bar.sync %0, %1;" ::"r"(id), "r"(n) : "memory");
}
__device__ __forceinline__ void named_bar_arrive(int id, int n) {
    asm volatile("bar.arrive %0, %1;" ::"r"(id), "r"(n) : "memory");
}

__global__ void __launch_bounds__(kThreads, 1)
mha_decode_kernel(const __nv_bfloat16* __restrict__ x, const __nv_bfloat16* __restrict__ kc,
                  const __nv_bfloat16* __restrict__ vc, const __nv_bfloat16* __restrict__ wq,
                  const __grid_constant__ CUtensorMap wo_map, __nv_bfloat16* __restrict__ out) {
    extern __shared__ __align__(1024) unsigned char smem[];
    const uint32_t sb = smem_u32(smem);
    const uint32_t bars = sb + kOffBar;
    volatile int2* desc = reinterpret_cast<volatile int2*>(smem + kOffDesc);
    volatile unsigned* s_epoch = reinterpret_cast<volatile unsigned*>(smem + kOffDesc + 2 * kCW * 8);

    const int tid = threadIdx.x, warp = tid >> 5, lane = tid & 31;
    const int cta = blockIdx.x, nctas = gridDim.x;
    const bool owner = cta < kOwners;
    const int g = lane >> 2, j = lane & 3;

    if (warp < kCW) {
        const uint32_t wq_s = sb + kOffW + warp * 8192, x_s = sb + kOffX + warp * 4096;
        if (owner) {
            const __nv_bfloat16* wp = wq + (size_t)(128 * warp + g) * kHD + 32 * cta + 8 * j;
            const uint32_t wd = wq_s + g * 64 + ((j ^ (g >> 1)) << 4);
#pragma unroll 4
            for (int s = 0; s < 16; s++) cp_async16(wd + s * 512, wp + (size_t)(8 * s) * kHD);
            const __nv_bfloat16* xp = x + (lane >> 4) * kD + 128 * warp + 8 * (lane & 15);
#pragma unroll 4
            for (int s = 0; s < 8; s++) {
                const int r = 2 * s + (lane >> 4);
                cp_async16(x_s + r * 256 + (((lane & 15) ^ (r & 7)) << 4), xp + 2 * s * kD);
            }
        }
        if (tid == 32) TS(15);
        named_bar_sync(0, kThreads);
        const unsigned epoch = *s_epoch;
        if (tid == 32) TS(10);
        if (owner) {
            asm volatile("cp.async.wait_all;" ::: "memory");
            __syncwarp();
            if (tid == 32) TS(11);
            if (kWin0 < 64 && lane == 0) mbar_arrive(bars + kBarWq * 8);
            float c[4][4];
#pragma unroll
            for (int t = 0; t < 4; t++) { c[t][0] = c[t][1] = c[t][2] = c[t][3] = 0.f; }
            const uint32_t xa = x_s + (lane & 15) * 256 + (((lane >> 4) ^ (lane & 7)) << 4);
            const uint32_t wa = wq_s + (lane & 15) * 64 + (((lane >> 4) ^ ((lane >> 1) & 3)) << 4);
#pragma unroll 2
            for (int s = 0; s < 8; s++) {
                uint32_t a0, a1, a2, a3, b0, b1, b2, b3;
                ldsm_x4(a0, a1, a2, a3, xa ^ (uint32_t)(s << 5));
                ldsm_x4_t(b0, b1, b2, b3, wa + s * 1024);
                mma_bf16(c[0], a0, a1, a2, a3, b0, b1);
                mma_bf16(c[1], a0, a1, a2, a3, b2, b3);
                ldsm_x4_t(b0, b1, b2, b3, (wa ^ 32u) + s * 1024);
                mma_bf16(c[2], a0, a1, a2, a3, b0, b1);
                mma_bf16(c[3], a0, a1, a2, a3, b2, b3);
            }
            __syncwarp();
            float* red = reinterpret_cast<float*>(smem + kOffW + warp * 8192) + g * 40 + 2 * j;
#pragma unroll
            for (int t = 0; t < 4; t++) {
                *reinterpret_cast<float2*>(red + 8 * t) = make_float2(c[t][0], c[t][1]);
                *reinterpret_cast<float2*>(red + 8 * 40 + 8 * t) = make_float2(c[t][2], c[t][3]);
            }
            named_bar_sync(1, kCW * 32);
            const float* rp = reinterpret_cast<const float*>(smem + kOffW) + (tid >> 4) * 40 + 2 * (tid & 15);
            float s0 = 0.f, s1 = 0.f;
#pragma unroll
            for (int w = 0; w < kCW; w++) {
                const float2 v = *reinterpret_cast<const float2*>(rp + w * 2048);
                s0 += v.x; s1 += v.y;
            }
            asm volatile("fence.proxy.async.shared::cta;" ::: "memory");
            st_relaxed_u64(g_q + (tid >> 4) * (kHD / 2) + 16 * cta + (tid & 15),
                           ((unsigned long long)epoch << 32) | pack_bf16(s0, s1));
            if (tid == 0) TS(2);
        }

        const uint32_t lane_off = (uint32_t)((((lane >> 3) & 1) * 8 + (lane & 7)) * 256 + (lane >> 4) * 128 + (lane & 7) * 16);
        const uint32_t lane_off_v = (uint32_t)(((lane >> 4) * 8 + (lane & 7)) * 256 + ((lane >> 3) & 1) * 128 + (lane & 7) * 16);
        const bool diag = (j == (g >> 1));
        const bool odd = (g & 1) != 0;
        const uint32_t pmask = diag ? (odd ? 0xffff0000u : 0x0000ffffu) : 0u;
        const float kScale = 0.08838834764831845f * 1.4426950408889634f;
        const uint32_t my_full = bars + (kBarFull + warp * 4) * 8;

        {
            {
                uint32_t ph = 0;
                bool ll_ok = false;
                for (;;) {
                    if (lane == 0) mbar_arrive(bars + (kBarInfo + warp) * 8);
                    mbar_wait(bars + (kBarInfo + warp) * 8, ph);
                    const int chunk = desc[ph * kCW + warp].x;
                    int slot = desc[ph * kCW + warp].y;
                    if (chunk < 0) break;
                    const bool big = chunk < kBigChunks;
                    const int pair = big ? (chunk >> 4) : kBigPairs + ((chunk - kBigChunks) >> 5);
                    uint32_t q0[8], q1[8];
                    {
                        const unsigned long long* qp = g_q + (pair >> 5) * (kHD / 2) + (pair & 31) * (kDh / 2) + j;
                        unsigned spins = 0;
                        for (;;) {
                            bool ok = true;
#pragma unroll
                            for (int t = 0; t < 8; t++) {
                                const unsigned long long a = ld_relaxed_u64(qp + 4 * (t ^ g));
                                const unsigned long long b = ld_relaxed_u64(qp + 32 + 4 * (t ^ g));
                                q0[t] = (uint32_t)a; q1[t] = (uint32_t)b;
                                ok = ok & ((uint32_t)(a >> 32) == epoch) & ((uint32_t)(b >> 32) == epoch);
                            }
                            if (__all_sync(0xffffffffu, ok)) break;
                            poll_tick(spins);
                        }
                    }
                    float s[8][2];
#pragma unroll
                    for (int kt = 0; kt < 2; kt++) {
                        if (kt == 0 || big) {
                            mbar_wait(my_full + kt * 8, ph);
                            const uint32_t base = sb + kOffRing + slot * kTileBytes;
                            float c[4][4];
#pragma unroll
                            for (int mt = 0; mt < 4; mt++) { c[mt][0] = c[mt][1] = c[mt][2] = c[mt][3] = 0.f; }
#pragma unroll
                            for (int t = 0; t < 8; t++) {
                                const uint32_t a = base + (lane_off ^ (uint32_t)(t << 4));
#pragma unroll
                                for (int mt = 0; mt < 4; mt++) {
                                    uint32_t r0, r1, r2, r3;
                                    ldsm_x4(r0, r1, r2, r3, a + mt * 4096);
                                    mma_bf16(c[mt], r0, r1, r2, r3, q0[t], q1[t]);
                                }
                            }
                            __syncwarp();
                            if (lane == 0) mbar_arrive(bars + (kBarEmpty + slot) * 8);
                            if (++slot == kSlots) slot = 0;
#pragma unroll
                            for (int mt = 0; mt < 4; mt++) {
                                s[kt * 4 + mt][0] = odd ? c[mt][1] : c[mt][0];
                                s[kt * 4 + mt][1] = odd ? c[mt][3] : c[mt][2];
                            }
                        } else {
#pragma unroll
                            for (int mt = 0; mt < 4; mt++) s[kt * 4 + mt][0] = s[kt * 4 + mt][1] = -INFINITY;
                        }
                    }
                    float m = s[0][0];
#pragma unroll
                    for (int i = 0; i < 8; i++) m = fmaxf(m, fmaxf(s[i][0], s[i][1]));
                    m = diag ? m : -INFINITY;
#pragma unroll
                    for (int d = 1; d < 32; d <<= 1) m = fmaxf(m, __shfl_xor_sync(0xffffffffu, m, d));
                    m *= kScale;
                    uint32_t p0[8], p1[8];
                    float l = 0.f;
#pragma unroll
                    for (int i = 0; i < 8; i++) {
                        const float e0 = ex2(fmaf(s[i][0], kScale, -m));
                        const float e1 = ex2(fmaf(s[i][1], kScale, -m));
                        l += e0 + e1;
                        p0[i] = pack_bf16(e0, e0) & pmask;
                        p1[i] = pack_bf16(e1, e1) & pmask;
                    }
                    l = diag ? l : 0.f;
#pragma unroll
                    for (int d = 1; d < 32; d <<= 1) l += __shfl_xor_sync(0xffffffffu, l, d);

                    float o[8][4];
#pragma unroll
                    for (int t = 0; t < 8; t++) { o[t][0] = o[t][1] = o[t][2] = o[t][3] = 0.f; }
#pragma unroll
                    for (int vt = 0; vt < 2; vt++) {
                        if (vt == 0 || big) {
                            mbar_wait(my_full + (2 + vt) * 8, ph);
                            const uint32_t base = sb + kOffRing + slot * kTileBytes;
#pragma unroll
                            for (int kk = 0; kk < 4; kk++) {
#pragma unroll
                                for (int t = 0; t < 8; t++) {
                                    uint32_t r0, r1, r2, r3;
                                    ldsm_x4_t(r0, r1, r2, r3, base + (lane_off_v ^ (uint32_t)(t << 4)) + kk * 4096);
                                    mma_bf16(o[t], r0, r1, r2, r3, p0[vt * 4 + kk], p1[vt * 4 + kk]);
                                }
                            }
                            __syncwarp();
                            if (lane == 0) mbar_arrive(bars + (kBarEmpty + slot) * 8);
                            if (++slot == kSlots) slot = 0;
                        }
                    }
                    float4 r;
                    {
                        float ylo[8], yhi[8];
#pragma unroll
                        for (int t = 0; t < 8; t++) { ylo[t] = o[t][0] + o[t ^ 1][1]; yhi[t] = o[t][2] + o[t ^ 1][3]; }
                        r.x = ylo[0]; r.y = ylo[1]; r.z = yhi[0]; r.w = yhi[1];
#pragma unroll
                        for (int d = 1; d < 4; d++) {
                            r.x += __shfl_xor_sync(0xffffffffu, ylo[2 * d], d);
                            r.y += __shfl_xor_sync(0xffffffffu, ylo[2 * d + 1], d);
                            r.z += __shfl_xor_sync(0xffffffffu, yhi[2 * d], d);
                            r.w += __shfl_xor_sync(0xffffffffu, yhi[2 * d + 1], d);
                        }
                    }
                    if (lane == 0) TS(9);
                    const bool last_row = chunk >= kLastRec;
                    if (last_row && !ll_ok) { mbar_wait(bars + kBarLL * 8, 0); ll_ok = true; }
                    unsigned* pp = g_part + (size_t)chunk * kPartStride;
                    const float il = rcp(l);
                    st_relaxed_v2(pp + 2 * lane, make_uint2(payload(pack_bf16(r.x * il, r.y * il)), payload(pack_bf16(r.z * il, r.w * il))));
                    if (lane < 4) st_relaxed_v2(pp + 64 + 2 * lane, make_uint2(payload(m), payload(l)));
                    if (!last_row) {
                        __syncwarp();
                        if (lane == 0) red_release_add(&g_paircnt[pair * 8], 1u);
                    }
                    ph ^= 1;
                }
            }

            if (owner) {
                const int h = cta >> 2, qt = cta & 3;
                mbar_wait(bars + kBarO * 8, 0);
                uint32_t af[8][4];
                const uint32_t aaddr = sb + kOffO + min(lane & 15, kB - 2) * kOPitch + (lane >> 4) * 16;
#pragma unroll
                for (int ks = 0; ks < 8; ks++) ldsm_x4(af[ks][0], af[ks][1], af[ks][2], af[ks][3], aaddr + ks * 32);
                float c[4][4], c2[4][4];
#pragma unroll
                for (int t = 0; t < 4; t++) { c[t][0] = c[t][1] = c[t][2] = c[t][3] = 0.f; c2[t][0] = c2[t][1] = c2[t][2] = c2[t][3] = 0.f; }
                const uint32_t baddr = sb + kOffW + (warp >> 1) * 4096 + ((lane & 7) + (lane >> 4) * 8) * 128 +
                                       (((4 * (warp & 1) + ((lane >> 3) & 1)) ^ (lane & 7)) << 4);
                uint32_t bw[8][2][4];
                uint4* const dst = g_ll + ((size_t)((16 * warp + qt) * 32 + h) * 32 + lane);
                const int pair15 = (kB - 1) * kH + h, hf = lane >> 4;
                const bool four = pair15 >= kBigPairs;
                const unsigned* rec = g_part + (size_t)(four ? kBigChunks + (pair15 - kBigPairs) * 32 + 4 * warp
                                                             : pair15 * 16 + 2 * warp) * kPartStride;
                const unsigned* up = rec + hf * kPartStride + (lane & 15) * 4;
                asm volatile("" : "+l"(rec), "+l"(up));
                auto piece = [&](int k) {
#pragma unroll
                    for (int i = 0; i < 4; i++) {
                        uint32_t(&r)[4] = bw[2 * k + (i >> 1)][i & 1];
                        ldsm_x4_t(r[0], r[1], r[2], r[3], (baddr ^ (uint32_t)((i & 1) << 5)) + k * 16384 + (i >> 1) * 2048);
                    }
#pragma unroll
                    for (int t = 0; t < 4; t++) {
                        mma_bf16(c[t], af[2 * k][0], af[2 * k][1], af[2 * k][2], af[2 * k][3],
                                 bw[2 * k][t >> 1][t & 1], bw[2 * k][t >> 1][2 + (t & 1)]);
                        mma_bf16(c2[t], af[2 * k + 1][0], af[2 * k + 1][1], af[2 * k + 1][2], af[2 * k + 1][3],
                                 bw[2 * k + 1][t >> 1][t & 1], bw[2 * k + 1][t >> 1][2 + (t & 1)]);
                    }
                };
                int wk = 0;
                bool merged = false;
                unsigned spins = 0;
                do {
                    uint4 u0, u1 = make_uint4(0u, 0u, 0u, 0u);
                    uint2 ml[4];
                    ml[2] = ml[3] = make_uint2(0xff800000u, 0u);
                    if (!merged) {
                        u0 = ld_relaxed_v4(up);
                        ml[0] = ld_relaxed_v2(rec + 64);
                        ml[1] = ld_relaxed_v2(rec + kPartStride + 64);
                        if (four) {
                            u1 = ld_relaxed_v4(up + 2 * kPartStride);
                            ml[2] = ld_relaxed_v2(rec + 2 * kPartStride + 64);
                            ml[3] = ld_relaxed_v2(rec + 3 * kPartStride + 64);
                        }
                    }
#pragma unroll
                    for (int k = 0; k < 3; k++)
                        if (wk == k && mbar_test(bars + (kBarWo + k) * 8, 0)) {
                            piece(k);
                            wk = k + 1;
                        }
                    if (!merged) {
                        const unsigned t = __vimax3_u32(
                            __vimax3_u32(__vimax3_u32(u0.x, u0.y, u0.z), __vimax3_u32(u0.w, u1.x, u1.y), max(u1.z, u1.w)),
                            __vimax3_u32(__vimax3_u32(ml[0].x, ml[0].y, ml[1].x), ml[1].y, ml[2].x),
                            __vimax3_u32(ml[2].y, ml[3].x, ml[3].y));
                        if (__all_sync(0xffffffffu, t != kEmpty)) {
                            const float m = fmaxf(fmaxf(__uint_as_float(ml[0].x), __uint_as_float(ml[1].x)),
                                                  fmaxf(__uint_as_float(ml[2].x), __uint_as_float(ml[3].x)));
                            float wgt[4];
#pragma unroll
                            for (int i = 0; i < 4; i++) wgt[i] = __uint_as_float(ml[i].y) * ex2(__uint_as_float(ml[i].x) - m);
                            const float f0 = hf ? wgt[1] : wgt[0], f1 = hf ? wgt[3] : wgt[2];
                            const unsigned keep0 = hf ? u0.z : u0.x, keep1 = hf ? u0.w : u0.y, keep2 = hf ? u1.z : u1.x, keep3 = hf ? u1.w : u1.y;
                            const unsigned give0 = hf ? u0.x : u0.z, give1 = hf ? u0.y : u0.w, give2 = hf ? u1.x : u1.z, give3 = hf ? u1.y : u1.w;
                            float4 v;
                            v.x = __shfl_xor_sync(0xffffffffu, f0 * __uint_as_float(give0 << 16) + f1 * __uint_as_float(give2 << 16), 16);
                            v.y = __shfl_xor_sync(0xffffffffu, f0 * __uint_as_float(give0 & 0xffff0000u) + f1 * __uint_as_float(give2 & 0xffff0000u), 16);
                            v.z = __shfl_xor_sync(0xffffffffu, f0 * __uint_as_float(give1 << 16) + f1 * __uint_as_float(give3 << 16), 16);
                            v.w = __shfl_xor_sync(0xffffffffu, f0 * __uint_as_float(give1 & 0xffff0000u) + f1 * __uint_as_float(give3 & 0xffff0000u), 16);
                            v.x += f0 * __uint_as_float(keep0 << 16) + f1 * __uint_as_float(keep2 << 16);
                            v.y += f0 * __uint_as_float(keep0 & 0xffff0000u) + f1 * __uint_as_float(keep2 & 0xffff0000u);
                            v.z += f0 * __uint_as_float(keep1 << 16) + f1 * __uint_as_float(keep3 << 16);
                            v.w += f0 * __uint_as_float(keep1 & 0xffff0000u) + f1 * __uint_as_float(keep3 & 0xffff0000u);
                            *reinterpret_cast<float4*>(smem + kOffMrg + warp * 512 + lane * 16) = v;
                            if (lane == 0)
                                *reinterpret_cast<float2*>(smem + kOffMrg + 4096 + warp * 8) = make_float2(m, (wgt[0] + wgt[1]) + (wgt[2] + wgt[3]));
                            __syncwarp();
                            if (lane == 0) mbar_arrive(bars + kBarMrg * 8);
                            merged = true;
                            CK_(4);
                        }
                    }
                    poll_tick(spins);
                } while (!merged || wk < 3);
                float d[4][4];
#pragma unroll
                for (int t = 0; t < 4; t++) { d[t][0] = d[t][1] = d[t][2] = d[t][3] = 0.f; }
                uint4 ov3;
                auto row15 = [&](int k, const uint4& ov) {
#pragma unroll
                    for (int u = 0; u < 2; u++) {
                        mma_bf16(d[u], bw[2 * k][u][0], bw[2 * k][u][1], bw[2 * k][u][2], bw[2 * k][u][3], ov.x, ov.y);
                        mma_bf16(d[2 + u], bw[2 * k + 1][u][0], bw[2 * k + 1][u][1], bw[2 * k + 1][u][2], bw[2 * k + 1][u][3], ov.z, ov.w);
                    }
                };
                auto row15_head = [&]() {
#pragma unroll
                    for (int k = 0; k < 3; k++) row15(k, *reinterpret_cast<const uint4*>(smem + kOffRow + j * 64 + k * 16));
                    ov3 = *reinterpret_cast<const uint4*>(smem + kOffRow + j * 64 + 48);
                };
                auto send_rows = [&]() {
#pragma unroll
                    for (int t = 0; t < 4; t++)
                        st_relaxed_v4(dst + t * 4 * 32 * 32,
                                      make_uint4(payload(c[t][0] + c2[t][0]), payload(c[t][1] + c2[t][1]),
                                                 payload(c[t][2] + c2[t][2]), payload(c[t][3] + c2[t][3])));
                };
                auto send_row15 = [&]() {
                    const float lo = (j & 1) ? d[0][2] + d[2][2] : d[0][0] + d[2][0];
                    const float hi = (j & 1) ? d[1][2] + d[3][2] : d[1][0] + d[3][0];
                    st_relaxed(g_ll15 + (((4 * warp + j) * 4 + qt) * 32 + h) * 8 + g, payload((j & 2) ? hi : lo));
                };
                for (;;) {
                    if (mbar_test(bars + kBarO15 * 8, 0)) {
                        row15_head();
                        mbar_wait(bars + (kBarWo + 3) * 8, 0);
                        CK_(0);
                        piece(3);
                        row15(3, ov3);
                        send_rows();
                        send_row15();
                        break;
                    }
                    if (mbar_test(bars + (kBarWo + 3) * 8, 0)) {
                        piece(3);
                        send_rows();
                        mbar_wait(bars + kBarO15 * 8, 0);
                        CK_(0);
                        row15_head();
                        row15(3, ov3);
                        send_row15();
                        break;
                    }
                    poll_tick(spins);
                }
                CK_(2);
                float a4[4];
                {
                    const uint4* src = g_ll + ((size_t)cta * 32 + 4 * warp) * 32 + lane;
                    uint4 v[4];
                    unsigned r15;
                    for (;;) {
#pragma unroll
                        for (int k = 0; k < 4; k++) v[k] = LDOUT(src + k * 32);
                        r15 = ld_relaxed(g_ll15 + cta * 256 + tid);
                        if (__all_sync(0xffffffffu, written(v[0]) & written(v[1]) & written(v[2]) & written(v[3]) & (r15 != kEmpty))) break;
                        poll_tick(spins);
                    }
                    float s15 = __uint_as_float(r15);
                    s15 += __shfl_xor_sync(0xffffffffu, s15, 8);
                    s15 += __shfl_xor_sync(0xffffffffu, s15, 16);
                    const float e0 = __shfl_sync(0xffffffffu, s15, 2 * j), e1 = __shfl_sync(0xffffffffu, s15, 2 * j + 1);
                    a4[0] = (__uint_as_float(v[0].x) + __uint_as_float(v[1].x)) + (__uint_as_float(v[2].x) + __uint_as_float(v[3].x));
                    a4[1] = (__uint_as_float(v[0].y) + __uint_as_float(v[1].y)) + (__uint_as_float(v[2].y) + __uint_as_float(v[3].y));
                    a4[2] = (__uint_as_float(v[0].z) + __uint_as_float(v[1].z)) + (__uint_as_float(v[2].z) + __uint_as_float(v[3].z));
                    a4[3] = (__uint_as_float(v[0].w) + __uint_as_float(v[1].w)) + (__uint_as_float(v[2].w) + __uint_as_float(v[3].w));
                    if (g == 7) { a4[2] = e0; a4[3] = e1; }
                }
                CK_(5);
                float* red = reinterpret_cast<float*>(smem + kOffRed);
                *reinterpret_cast<float4*>(red + warp * 128 + lane * 4) = make_float4(a4[0], a4[1], a4[2], a4[3]);
                named_bar_sync(1, kCW * 32);
                CK_(6);
                if (tid < 64) {
                    float s0 = 0.f, s1 = 0.f;
#pragma unroll
                    for (int w = 0; w < kCW; w++) {
                        const float2 v = *reinterpret_cast<const float2*>(red + w * 128 + tid * 2);
                        s0 += v.x; s1 += v.y;
                    }
                    const int ln = tid >> 1, b = (ln >> 2) + (tid & 1) * 8;
                    const int col = qt * 256 + h * 8 + 2 * (ln & 3);
                    *reinterpret_cast<uint32_t*>(out + b * kD + col) = pack_bf16(s0, s1);
                    if (cta == 0 && tid == 0) g_epoch = epoch;
                }
            }
        }
    } else if (warp == kCW) {
        if (lane == 0) {
            TS(0);
#pragma unroll
            for (int i = 0; i < kNumBars; i++)
                mbar_init(bars + i * 8, i == kBarWq || i == kBarMrg ? kCW : (i >= kBarInfo && i < kBarEmpty ? 2 : 1));
            asm volatile("fence.mbarrier_init.release.cluster;" ::: "memory");
        }
        __syncwarp();
        uint64_t pol;
        asm volatile("createpolicy.fractional.L2::evict_first.b64 %0, 1.0;" : "=l"(pol));
        named_bar_arrive(0, kThreads);
        int slot = 0;
        uint32_t eph = 1;
        uint32_t fifo[kMaxWin];
#pragma unroll
        for (int k = 0; k < kMaxWin; k++) fifo[k] = 0;
        int win = kWin;
        auto throttle = [&](uint32_t next) {
            uint32_t f = fifo[0];
#pragma unroll
            for (int k = 1; k < kMaxWin; k++) f = (win == kMaxWin - k) ? fifo[k] : f;
            if (f) mbar_wait(f & ~1u, f & 1u);
#pragma unroll
            for (int k = 0; k + 1 < kMaxWin; k++) fifo[k] = fifo[k + 1];
            fifo[kMaxWin - 1] = next;
        };
        int wk = 0;
        auto wo_piece = [&]() {
            const uint32_t wb = bars + (kBarWo + wk) * 8;
            throttle(wb);
            mbar_expect_tx(wb, 16384);
#pragma unroll
            for (int c = 0; c < 4; c++)
                asm volatile("cp.async.bulk.tensor.2d.shared::cluster.global.mbarrier::complete_tx::bytes.L2::cache_hint"
                             " [%0], [%1, {%3, %4}], [%2], %5;"
                             ::"r"(sb + kOffW + wk * 16384 + c * 4096), "l"(&wo_map), "r"(wb),
                               "r"((cta & 3) * 256 + c * 64), "r"((cta >> 2) * 128 + wk * 32), "l"(pol) : "memory");
            wk++;
        };
        if (lane == 0) {
            int cur = cta, nxt = 0, i = 0, n = 0;
            while (cur < kChunks) {
                const int w = i & (kCW - 1);
                const uint32_t ph = (uint32_t)(i >> 3) & 1u;
                desc[ph * kCW + w].x = cur; desc[ph * kCW + w].y = slot;
                mbar_arrive(bars + (kBarInfo + w) * 8);
                const int rem = kChunks - cur;
                if (rem <= MHA_RWO + 400) asm volatile("prefetch.tensormap [%0];" ::"l"(&wo_map) : "memory");
                if (rem <= MHA_R3) win = rem <= MHA_R1 ? MHA_WA : (rem <= MHA_R2 ? MHA_WB : MHA_WC);
                const bool big = cur < kBigChunks;
                const size_t off = big ? (size_t)cur * (128 * kDh) : (size_t)(cur + kBigChunks) * (64 * kDh);
#pragma unroll
                for (int t = 0; t < 4; t++) {
                    if ((t & 1) == 0 || big) {
                        if (kWin0 < 64 && n == kWin0 && owner) mbar_wait(bars + kBarWq * 8, 0);
                        const uint32_t fb = bars + (kBarFull + w * 4 + t) * 8;
                        throttle(fb | ph);
                        mbar_wait(bars + (kBarEmpty + slot) * 8, eph);
                        mbar_expect_tx(fb, kTileBytes);
                        const __nv_bfloat16* src = (t < 2 ? kc : vc) + off + (t & 1) * (64 * kDh);
                        bulk_load(sb + kOffRing + slot * kTileBytes, src, kTileBytes, fb, pol);
                        n++;
                        if (++slot == kSlots) { slot = 0; eph ^= 1; }
                    }
                    if (t == (big ? 2 : 0)) {
                        const unsigned v = atomicAdd(&g_work, 1u);
                        if (v == (unsigned)(kChunks - 1)) g_work = 0;
                        nxt = (int)v + nctas;
                    }
                }
                if (MHA_EARLY > 0 && owner && rem <= MHA_RWO) {
#pragma unroll 1
                    while (wk < MHA_EARLY) wo_piece();
                }
                cur = nxt;
                i++;
            }
            for (int k = 0; k < kCW; k++, i++) {
                const int w = i & (kCW - 1);
                desc[((i >> 3) & 1) * kCW + w].x = -1;
                mbar_arrive(bars + (kBarInfo + w) * 8);
            }
            TS(1);
        }
        if (owner && lane == 0) {
#pragma unroll 1
            while (wk < 4) {
                win = wk == 0 ? MHA_WWO0 : MHA_WWO;
                wo_piece();
            }
            TS(13);
        }
    } else {
        if (lane == 0) { *s_epoch = ld_relaxed(&g_epoch) + 1u; TS(14); }
        __syncwarp();
        named_bar_sync(0, kThreads);
        const unsigned epoch = *s_epoch;
        const int h = cta >> 2;
#pragma unroll 1
        for (int b = 0; b < kB; b++) {
            if (b == kB - 4 && owner) {
                const uint4 e = make_uint4(kEmpty, kEmpty, kEmpty, kEmpty);
                uint4* inbox = g_ll + (size_t)cta * 1024;
#pragma unroll 4
                for (int k = 0; k < 32; k++) __stcg(inbox + k * 32 + lane, e);
                uint4* inbox15 = reinterpret_cast<uint4*>(g_ll15 + cta * 256);
                __stcg(inbox15 + lane, e);
                __stcg(inbox15 + 32 + lane, e);
                constexpr int kVec = (kChunks - kLastRec) * (kPartStride / 4);
                uint4* lastp = reinterpret_cast<uint4*>(g_part + (size_t)kLastRec * kPartStride);
                for (int k = cta * 32 + lane; k < kVec; k += kOwners * 32) __stcg(lastp + k, e);
                __syncwarp();
                if (lane == 0) red_release_add(&g_cleared, 1u);
            }
            if (b == kB - 2) {
                if (lane == 0) {
                    unsigned spins = 0;
                    while (ld_acquire(&g_cleared) != epoch * (unsigned)kOwners) {
                        __nanosleep(500);
                        poll_tick(spins);
                    }
                    mbar_arrive(bars + kBarLL * 8);
                }
                __syncwarp();
            }
            if (!owner) continue;
            const int hf = lane >> 4;
            float v[4];
            if (b != kB - 1) {
                const int pair = b * kH + h;
                if (lane == 0) {
                    unsigned spins = 0;
                    while (ld_acquire(&g_paircnt[pair * 8]) != epoch * 16u) {
                        __nanosleep(400);
                        poll_tick(spins);
                    }
                }
                __syncwarp();
                const unsigned* rec = g_part + (size_t)(pair * 16) * kPartStride;
                uint4 u[8];
#pragma unroll
                for (int i = 0; i < 8; i++) u[i] = ld_relaxed_v4(rec + (2 * i + hf) * kPartStride + (lane & 15) * 4);
                const uint2 mu = ld_relaxed_v2(rec + (lane & 15) * kPartStride + 64);
                float m = __uint_as_float(mu.x);
#pragma unroll
                for (int d = 1; d < 16; d <<= 1) m = fmaxf(m, __shfl_xor_sync(0xffffffffu, m, d));
                const float wgt = __uint_as_float(mu.y) * ex2(__uint_as_float(mu.x) - m);
                float acc[8], l = 0.f;
#pragma unroll
                for (int k = 0; k < 8; k++) acc[k] = 0.f;
#pragma unroll
                for (int i = 0; i < 8; i++) {
                    const float f = __shfl_sync(0xffffffffu, wgt, 2 * i + hf);
                    l += f;
                    acc[0] += f * __uint_as_float(u[i].x << 16); acc[1] += f * __uint_as_float(u[i].x & 0xffff0000u);
                    acc[2] += f * __uint_as_float(u[i].y << 16); acc[3] += f * __uint_as_float(u[i].y & 0xffff0000u);
                    acc[4] += f * __uint_as_float(u[i].z << 16); acc[5] += f * __uint_as_float(u[i].z & 0xffff0000u);
                    acc[6] += f * __uint_as_float(u[i].w << 16); acc[7] += f * __uint_as_float(u[i].w & 0xffff0000u);
                }
                const float inv = rcp(l + __shfl_xor_sync(0xffffffffu, l, 16));
#pragma unroll
                for (int k = 0; k < 4; k++)
                    v[k] = ((hf ? acc[4 + k] : acc[k]) + __shfl_xor_sync(0xffffffffu, hf ? acc[k] : acc[4 + k], 16)) * inv;
            } else {
                mbar_wait(bars + kBarMrg * 8, 0);
                if (lane == 0) TS(5);
                float2 ml[kCW];
#pragma unroll
                for (int w = 0; w < kCW; w += 2) {
                    const float4 t = *reinterpret_cast<const float4*>(smem + kOffMrg + 4096 + w * 8);
                    ml[w] = make_float2(t.x, t.y); ml[w + 1] = make_float2(t.z, t.w);
                }
                const float m = fmaxf(fmaxf(fmaxf(ml[0].x, ml[1].x), fmaxf(ml[2].x, ml[3].x)),
                                      fmaxf(fmaxf(ml[4].x, ml[5].x), fmaxf(ml[6].x, ml[7].x)));
                float l = 0.f;
                v[0] = v[1] = v[2] = v[3] = 0.f;
#pragma unroll
                for (int w = 0; w < kCW; w++) {
                    const float f = ex2(ml[w].x - m);
                    const float4 t = *reinterpret_cast<const float4*>(smem + kOffMrg + w * 512 + lane * 16);
                    l += f * ml[w].y;
                    v[0] += f * t.x; v[1] += f * t.y; v[2] += f * t.z; v[3] += f * t.w;
                }
                const float inv = rcp(l);
                v[0] *= inv; v[1] *= inv; v[2] *= inv; v[3] *= inv;
            }
            const int gw = (lane & 15) >> 1, jw = 2 * (lane & 1) + hf;
            __nv_bfloat16* orow = b != kB - 1
                ? reinterpret_cast<__nv_bfloat16*>(smem + kOffO + b * kOPitch) + 16 * jw + gw
                : reinterpret_cast<__nv_bfloat16*>(smem + kOffRow) + (gw >> 1) * 32 + jw * 4 + (gw & 1);
            const int s1 = b != kB - 1 ? 8 : 2, s2 = b != kB - 1 ? 64 : 16;
            orow[0] = __float2bfloat16(v[0]);
            orow[s1] = __float2bfloat16(v[1]);
            orow[s2] = __float2bfloat16(v[2]);
            orow[s1 + s2] = __float2bfloat16(v[3]);
            if (b >= kB - 2) {
                __syncwarp();
                if (lane == 0) { mbar_arrive(bars + (b == kB - 2 ? kBarO : kBarO15) * 8); TS(4); }
            }
        }
    }
}

}

extern "C" void kernel_launch(void* const* d_in, const int* in_sizes, int n_in, void* d_out, int out_size) {
    (void)in_sizes; (void)n_in; (void)out_size;
    static int sms = 0;
    static CUtensorMap wo_map;
    static const void* wo_seen = nullptr;
    if (sms == 0) {
        int dev = 0;
        cudaGetDevice(&dev);
        cudaDeviceGetAttribute(&sms, cudaDevAttrMultiProcessorCount, dev);
        cudaFuncSetAttribute(mha_decode_kernel, cudaFuncAttributeMaxDynamicSharedMemorySize, kSmemBytes);
    }
    if (wo_seen != d_in[4]) {
        typedef CUresult (*EncodeFn)(CUtensorMap*, CUtensorMapDataType, cuuint32_t, void*, const cuuint64_t*,
                                     const cuuint64_t*, const cuuint32_t*, const cuuint32_t*, CUtensorMapInterleave,
                                     CUtensorMapSwizzle, CUtensorMapL2promotion, CUtensorMapFloatOOBfill);
        void* fn = nullptr;
        cudaDriverEntryPointQueryResult qr;
        cudaGetDriverEntryPoint("cuTensorMapEncodeTiled", &fn, cudaEnableDefault, &qr);
        const cuuint64_t dims[2] = {(cuuint64_t)kD, (cuuint64_t)kHD}, strides[1] = {(cuuint64_t)kD * 2};
        const cuuint32_t box[2] = {64, 32}, estr[2] = {1, 1};
        ((EncodeFn)fn)(&wo_map, CU_TENSOR_MAP_DATA_TYPE_BFLOAT16, 2, d_in[4], dims, strides, box, estr,
                       CU_TENSOR_MAP_INTERLEAVE_NONE, CU_TENSOR_MAP_SWIZZLE_128B, CU_TENSOR_MAP_L2_PROMOTION_L2_128B,
                       CU_TENSOR_MAP_FLOAT_OOB_FILL_NONE);
        wo_seen = d_in[4];
    }
    mha_decode_kernel<<<sms, kThreads, kSmemBytes>>>(
        (const __nv_bfloat16*)d_in[0], (const __nv_bfloat16*)d_in[1], (const __nv_bfloat16*)d_in[2],
        (const __nv_bfloat16*)d_in[3], wo_map, (__nv_bfloat16*)d_out);
}
```

```cpp
#include <cuda_runtime.h>
#include <cuda.h>
#include <cuda_bf16.h>
#include <stdint.h>

namespace {

constexpr int kB = 16, kD = 1024, kH = 32, kSk = 2048, kDh = 128;
constexpr int kHD = kH * kDh;
constexpr int kBigPairs = (kB - 1) * kH;
constexpr int kBigChunks = kBigPairs * 16;
constexpr int kChunks = kBigChunks + kH * 32;
constexpr int kTileBytes = 16384;
constexpr int kSlots = 8;
constexpr int kWin = 3;
constexpr int kWinLast = 6;
constexpr int kWinWo = 2;
constexpr int kCW = 8;
constexpr int kThreads = (kCW + 2) * 32;
constexpr int kOwners = 128;
constexpr int kOPitch = 272;
constexpr int kRec = 72;
constexpr unsigned kEmpty = 0xffffffffu;

constexpr int kOffW = kSlots * kTileBytes;
constexpr int kOffX = kOffW + 65536;
constexpr int kOffO = kOffX;
constexpr int kOffRed = kOffX + 8192;
constexpr int kOffRow = kOffX + 12288;
constexpr int kOffMrg = kOffX + 16384;
constexpr int kOffBar = kOffX + 32768;
constexpr int kBarFull = 0, kBarInfo = kCW * 4, kBarEmpty = kBarInfo + kCW, kBarO = kBarEmpty + kSlots,
              kBarO15 = kBarO + 1, kBarMrg = kBarO15 + 1, kBarClr = kBarMrg + 1, kBarWo = kBarClr + 1,
              kNumBars = kBarWo + 4;
constexpr int kOffDesc = kOffBar + kNumBars * 8;
constexpr int kSmemBytes = kOffDesc + 2 * kCW * 8 + 16;
static_assert(kSmemBytes <= 232448, "shared memory budget");

constexpr unsigned kPollLimit = 1u << 23;

__device__ unsigned g_epoch;
__device__ unsigned g_work;
__device__ unsigned g_cleared;
__device__ unsigned g_paircnt[kBigPairs * 8];
__device__ __align__(128) unsigned long long g_q[kB * kHD / 2];
__device__ __align__(128) unsigned g_part[kChunks * kRec];
__device__ __align__(128) uint2 g_mail[kOwners * 32 * 32];

__device__ __forceinline__ uint32_t smem_u32(const void* p) { return (uint32_t)__cvta_generic_to_shared(p); }
__device__ __forceinline__ void mbar_init(uint32_t bar, uint32_t cnt) {
    asm volatile("mbarrier.init.shared::cta.b64 [%0], %1;" ::"r"(bar), "r"(cnt) : "memory");
}
__device__ __forceinline__ void mbar_expect_tx(uint32_t bar, uint32_t bytes) {
    asm volatile("mbarrier.arrive.expect_tx.shared::cta.b64 _, [%0], %1;" ::"r"(bar), "r"(bytes) : "memory");
}
__device__ __forceinline__ void mbar_arrive(uint32_t bar) {
    asm volatile("mbarrier.arrive.shared::cta.b64 _, [%0];" ::"r"(bar) : "memory");
}
__device__ __forceinline__ void mbar_wait(uint32_t bar, uint32_t parity) {
    asm volatile("{\n.reg .pred p;\n.reg .u32 n;\nmov.u32 n, 0;\n"
                 "WAIT_LOOP:\nmbarrier.try_wait.parity.shared::cta.b64 p, [%0], %1;\n@p bra WAIT_DONE;\n"
                 "add.u32 n, n, 1;\nsetp.lt.u32 p, n, 0x400000;\n@p bra WAIT_LOOP;\ntrap;\nWAIT_DONE:\n}\n"
                 ::"r"(bar), "r"(parity) : "memory");
}
__device__ __forceinline__ bool mbar_test(uint32_t bar, uint32_t parity) {
    uint32_t ok;
    asm volatile("{\n.reg .pred p;\nmbarrier.test_wait.parity.shared::cta.b64 p, [%1], %2;\nselp.u32 %0, 1, 0, p;\n}\n"
                 : "=r"(ok) : "r"(bar), "r"(parity) : "memory");
    return ok != 0;
}
__device__ __forceinline__ void poll_tick(unsigned& n) {
    if (++n > kPollLimit) __trap();
}
__device__ __forceinline__ void cp_async16(uint32_t dst, const void* src) {
    asm volatile("cp.async.cg.shared.global.L2::128B [%0], [%1], 16;" ::"r"(dst), "l"(src) : "memory");
}
__device__ __forceinline__ void bulk_load(uint32_t dst, const void* src, uint32_t bytes, uint32_t bar, uint64_t pol) {
    asm volatile("cp.async.bulk.shared::cluster.global.mbarrier::complete_tx::bytes.L2::cache_hint [%0], [%1], %2, [%3], %4;"
                 ::"r"(dst), "l"(src), "r"(bytes), "r"(bar), "l"(pol) : "memory");
}
__device__ __forceinline__ void ldsm_x4(uint32_t& r0, uint32_t& r1, uint32_t& r2, uint32_t& r3, uint32_t addr) {
    asm volatile("ldmatrix.sync.aligned.m8n8.x4.shared.b16 {%0,%1,%2,%3}, [%4];"
                 : "=r"(r0), "=r"(r1), "=r"(r2), "=r"(r3) : "r"(addr) : "memory");
}
__device__ __forceinline__ void ldsm_x4_t(uint32_t& r0, uint32_t& r1, uint32_t& r2, uint32_t& r3, uint32_t addr) {
    asm volatile("ldmatrix.sync.aligned.m8n8.x4.trans.shared.b16 {%0,%1,%2,%3}, [%4];"
                 : "=r"(r0), "=r"(r1), "=r"(r2), "=r"(r3) : "r"(addr) : "memory");
}
__device__ __forceinline__ void mma_bf16(float (&c)[4], uint32_t a0, uint32_t a1, uint32_t a2, uint32_t a3,
                                         uint32_t b0, uint32_t b1) {
    asm volatile("mma.sync.aligned.m16n8k16.row.col.f32.bf16.bf16.f32 {%0,%1,%2,%3}, {%4,%5,%6,%7}, {%8,%9}, {%0,%1,%2,%3};"
                 : "+f"(c[0]), "+f"(c[1]), "+f"(c[2]), "+f"(c[3])
                 : "r"(a0), "r"(a1), "r"(a2), "r"(a3), "r"(b0), "r"(b1));
}
__device__ __forceinline__ uint32_t pack_bf16(float lo, float hi) {
    uint32_t r;
    asm("cvt.rn.bf16x2.f32 %0, %1, %2;" : "=r"(r) : "f"(hi), "f"(lo));
    return r;
}
__device__ __forceinline__ float ex2(float x) {
    float r;
    asm("ex2.approx.ftz.f32 %0, %1;" : "=f"(r) : "f"(x));
    return r;
}
__device__ __forceinline__ float rcp(float x) {
    float r;
    asm("rcp.approx.ftz.f32 %0, %1;" : "=f"(r) : "f"(x));
    return r;
}
__device__ __forceinline__ unsigned ld_relaxed(const unsigned* p) {
    unsigned v;
    asm volatile("ld.relaxed.gpu.global.u32 %0, [%1];" : "=r"(v) : "l"(p) : "memory");
    return v;
}
__device__ __forceinline__ unsigned long long ld_relaxed_u64(const unsigned long long* p) {
    unsigned long long v;
    asm volatile("ld.relaxed.gpu.global.b64 %0, [%1];" : "=l"(v) : "l"(p) : "memory");
    return v;
}
__device__ __forceinline__ void st_relaxed_u64(unsigned long long* p, unsigned long long v) {
    asm volatile("st.relaxed.gpu.global.b64 [%0], %1;" ::"l"(p), "l"(v) : "memory");
}
__device__ __forceinline__ uint2 ld_relaxed_v2(const void* p) {
    uint2 v;
    asm volatile("ld.relaxed.gpu.global.v2.u32 {%0,%1}, [%2];" : "=r"(v.x), "=r"(v.y) : "l"(p) : "memory");
    return v;
}
__device__ __forceinline__ void st_relaxed_v2(void* p, uint2 v) {
    asm volatile("st.relaxed.gpu.global.v2.u32 [%0], {%1,%2};" ::"l"(p), "r"(v.x), "r"(v.y) : "memory");
}
__device__ __forceinline__ unsigned ld_acquire(const unsigned* p) {
    unsigned v;
    asm volatile("ld.acquire.gpu.global.u32 %0, [%1];" : "=r"(v) : "l"(p) : "memory");
    return v;
}
__device__ __forceinline__ void red_release_add(unsigned* p, unsigned v) {
    asm volatile("red.release.gpu.global.add.u32 [%0], %1;" ::"l"(p), "r"(v) : "memory");
}
__device__ __forceinline__ uint4 ld_relaxed_v4(const void* p) {
    uint4 v;
    asm volatile("ld.relaxed.gpu.global.v4.u32 {%0,%1,%2,%3}, [%4];" : "=r"(v.x), "=r"(v.y), "=r"(v.z), "=r"(v.w) : "l"(p) : "memory");
    return v;
}
__device__ __forceinline__ unsigned payload(unsigned u) { return u == kEmpty ? 0x7fffffffu : u; }
__device__ __forceinline__ unsigned payload(float f) { return payload(__float_as_uint(f)); }
__device__ __forceinline__ float bf_lo(unsigned u) { return __uint_as_float(u << 16); }
__device__ __forceinline__ float bf_hi(unsigned u) { return __uint_as_float(u & 0xffff0000u); }
__device__ __forceinline__ void named_bar_sync(int id, int n) {
    asm volatile("bar.sync %0, %1;" ::"r"(id), "r"(n) : "memory");
}
__device__ __forceinline__ void named_bar_arrive(int id, int n) {
    asm volatile("bar.arrive %0, %1;" ::"r"(id), "r"(n) : "memory");
}

__global__ void __launch_bounds__(kThreads, 1)
mha_decode_kernel(const __nv_bfloat16* __restrict__ x, const __nv_bfloat16* __restrict__ kc,
                  const __nv_bfloat16* __restrict__ vc, const __nv_bfloat16* __restrict__ wq,
                  const __grid_constant__ CUtensorMap wo_map, __nv_bfloat16* __restrict__ out) {
    extern __shared__ __align__(1024) unsigned char smem[];
    const uint32_t sb = smem_u32(smem);
    const uint32_t bars = sb + kOffBar;
    volatile int2* desc = reinterpret_cast<volatile int2*>(smem + kOffDesc);
    volatile unsigned* s_epoch = reinterpret_cast<volatile unsigned*>(smem + kOffDesc + 2 * kCW * 8);

    const int tid = threadIdx.x, warp = tid >> 5, lane = tid & 31;
    const int cta = blockIdx.x, nctas = gridDim.x;
    const bool owner = cta < kOwners;
    const int g = lane >> 2, j = lane & 3, hf = lane >> 4;

    const uint32_t wq_s = sb + kOffW + warp * 8192, x_s = sb + kOffX + warp * 4096;
    if (warp < kCW && owner) {
        const __nv_bfloat16* wp = wq + (size_t)(128 * warp + g) * kHD + 32 * cta + 8 * j;
        const uint32_t wd = wq_s + g * 64 + ((j ^ (g >> 1)) << 4);
#pragma unroll
        for (int s = 0; s < 16; s++) cp_async16(wd + s * 512, wp + (size_t)(8 * s) * kHD);
    }

    if (warp < kCW) {
        if (owner) {
            const __nv_bfloat16* xp = x + hf * kD + 128 * warp + 8 * (lane & 15);
#pragma unroll 4
            for (int s = 0; s < 8; s++) {
                const int r = 2 * s + hf;
                cp_async16(x_s + r * 256 + (((lane & 15) ^ (r & 7)) << 4), xp + 2 * s * kD);
            }
        }
        named_bar_sync(0, kThreads);
        const unsigned epoch = *s_epoch;
        if (owner) {
            asm volatile("cp.async.wait_all;" ::: "memory");
            __syncwarp();
            float c[4][4];
#pragma unroll
            for (int t = 0; t < 4; t++) { c[t][0] = c[t][1] = c[t][2] = c[t][3] = 0.f; }
            const uint32_t xa = x_s + (lane & 15) * 256 + ((hf ^ (lane & 7)) << 4);
            const uint32_t wa = wq_s + (lane & 15) * 64 + ((hf ^ ((lane >> 1) & 3)) << 4);
#pragma unroll 2
            for (int s = 0; s < 8; s++) {
                uint32_t a0, a1, a2, a3, b0, b1, b2, b3;
                ldsm_x4(a0, a1, a2, a3, xa ^ (uint32_t)(s << 5));
                ldsm_x4_t(b0, b1, b2, b3, wa + s * 1024);
                mma_bf16(c[0], a0, a1, a2, a3, b0, b1);
                mma_bf16(c[1], a0, a1, a2, a3, b2, b3);
                ldsm_x4_t(b0, b1, b2, b3, (wa ^ 32u) + s * 1024);
                mma_bf16(c[2], a0, a1, a2, a3, b0, b1);
                mma_bf16(c[3], a0, a1, a2, a3, b2, b3);
            }
            __syncwarp();
            float* red = reinterpret_cast<float*>(smem + kOffW + warp * 8192) + g * 40 + 2 * j;
#pragma unroll
            for (int t = 0; t < 4; t++) {
                *reinterpret_cast<float2*>(red + 8 * t) = make_float2(c[t][0], c[t][1]);
                *reinterpret_cast<float2*>(red + 8 * 40 + 8 * t) = make_float2(c[t][2], c[t][3]);
            }
            named_bar_sync(1, kCW * 32);
            const float* rp = reinterpret_cast<const float*>(smem + kOffW) + (tid >> 4) * 40 + 2 * (tid & 15);
            float s0 = 0.f, s1 = 0.f;
#pragma unroll
            for (int w = 0; w < kCW; w++) {
                const float2 v = *reinterpret_cast<const float2*>(rp + w * 2048);
                s0 += v.x; s1 += v.y;
            }
            asm volatile("fence.proxy.async.shared::cta;" ::: "memory");
            st_relaxed_u64(g_q + (tid >> 4) * (kHD / 2) + 16 * cta + (tid & 15),
                           ((unsigned long long)epoch << 32) | pack_bf16(s0, s1));
        }

        const uint32_t off_k = (uint32_t)((((lane >> 3) & 1) * 8 + (lane & 7)) * 256 + hf * 128 + (lane & 7) * 16);
        const uint32_t off_v = (uint32_t)((hf * 8 + (lane & 7)) * 256 + ((lane >> 3) & 1) * 128 + (lane & 7) * 16);
        const bool diag = (j == (g >> 1));
        const bool odd = (g & 1) != 0;
        const uint32_t pmask = diag ? (odd ? 0xffff0000u : 0x0000ffffu) : 0u;
        const float kScale = 0.08838834764831845f, kLog2e = 1.4426950408889634f;
        const uint32_t my_full = bars + (kBarFull + warp * 4) * 8;
        uint32_t ph = 0;
        bool cleared = false;
        for (;;) {
            if (lane == 0) mbar_arrive(bars + (kBarInfo + warp) * 8);
            mbar_wait(bars + (kBarInfo + warp) * 8, ph);
            const int chunk = desc[ph * kCW + warp].x;
            int slot = desc[ph * kCW + warp].y;
            if (chunk < 0) break;
            const bool big = chunk < kBigChunks;
            const int pair = big ? (chunk >> 4) : kBigPairs + ((chunk - kBigChunks) >> 5);
            uint32_t q0[8], q1[8];
            {
                const unsigned long long* qp = g_q + (pair >> 5) * (kHD / 2) + (pair & 31) * (kDh / 2) + j;
                unsigned spins = 0;
                for (;;) {
                    bool ok = true;
#pragma unroll
                    for (int t = 0; t < 8; t++) {
                        const unsigned long long a = ld_relaxed_u64(qp + 4 * (t ^ g));
                        const unsigned long long b = ld_relaxed_u64(qp + 32 + 4 * (t ^ g));
                        q0[t] = (uint32_t)a; q1[t] = (uint32_t)b;
                        ok = ok & ((uint32_t)(a >> 32) == epoch) & ((uint32_t)(b >> 32) == epoch);
                    }
                    if (__all_sync(0xffffffffu, ok)) break;
                    poll_tick(spins);
                }
            }
            float s[8][2];
#pragma unroll
            for (int kt = 0; kt < 2; kt++) {
                if (kt == 0 || big) {
                    mbar_wait(my_full + kt * 8, ph);
                    const uint32_t base = sb + slot * kTileBytes;
                    float c[4][4];
#pragma unroll
                    for (int mt = 0; mt < 4; mt++) { c[mt][0] = c[mt][1] = c[mt][2] = c[mt][3] = 0.f; }
#pragma unroll
                    for (int t = 0; t < 8; t++) {
                        const uint32_t a = base + (off_k ^ (uint32_t)(t << 4));
#pragma unroll
                        for (int mt = 0; mt < 4; mt++) {
                            uint32_t r0, r1, r2, r3;
                            ldsm_x4(r0, r1, r2, r3, a + mt * 4096);
                            mma_bf16(c[mt], r0, r1, r2, r3, q0[t], q1[t]);
                        }
                    }
                    __syncwarp();
                    if (lane == 0) mbar_arrive(bars + (kBarEmpty + slot) * 8);
                    if (++slot == kSlots) slot = 0;
#pragma unroll
                    for (int mt = 0; mt < 4; mt++) {
                        const uint32_t qk = pack_bf16(odd ? c[mt][1] : c[mt][0], odd ? c[mt][3] : c[mt][2]);
                        const uint32_t sc = pack_bf16(bf_lo(qk) * kScale, bf_hi(qk) * kScale);
                        s[kt * 4 + mt][0] = bf_lo(sc);
                        s[kt * 4 + mt][1] = bf_hi(sc);
                    }
                } else {
#pragma unroll
                    for (int mt = 0; mt < 4; mt++) s[kt * 4 + mt][0] = s[kt * 4 + mt][1] = -INFINITY;
                }
            }
            float m = s[0][0];
#pragma unroll
            for (int i = 0; i < 8; i++) m = fmaxf(m, fmaxf(s[i][0], s[i][1]));
            m = diag ? m : -INFINITY;
#pragma unroll
            for (int d = 1; d < 32; d <<= 1) m = fmaxf(m, __shfl_xor_sync(0xffffffffu, m, d));
            m *= kLog2e;
            uint32_t p0[8], p1[8];
            float l = 0.f;
#pragma unroll
            for (int i = 0; i < 8; i++) {
                const float e0 = ex2(fmaf(s[i][0], kLog2e, -m));
                const float e1 = ex2(fmaf(s[i][1], kLog2e, -m));
                l += e0 + e1;
                p0[i] = pack_bf16(e0, e0) & pmask;
                p1[i] = pack_bf16(e1, e1) & pmask;
            }
            l = diag ? l : 0.f;
#pragma unroll
            for (int d = 1; d < 32; d <<= 1) l += __shfl_xor_sync(0xffffffffu, l, d);

            float o[8][4];
#pragma unroll
            for (int t = 0; t < 8; t++) { o[t][0] = o[t][1] = o[t][2] = o[t][3] = 0.f; }
#pragma unroll
            for (int vt = 0; vt < 2; vt++) {
                if (vt == 0 || big) {
                    mbar_wait(my_full + (2 + vt) * 8, ph);
                    const uint32_t base = sb + slot * kTileBytes;
#pragma unroll
                    for (int kk = 0; kk < 4; kk++) {
#pragma unroll
                        for (int t = 0; t < 8; t++) {
                            uint32_t r0, r1, r2, r3;
                            ldsm_x4_t(r0, r1, r2, r3, base + (off_v ^ (uint32_t)(t << 4)) + kk * 4096);
                            mma_bf16(o[t], r0, r1, r2, r3, p0[vt * 4 + kk], p1[vt * 4 + kk]);
                        }
                    }
                    __syncwarp();
                    if (lane == 0) mbar_arrive(bars + (kBarEmpty + slot) * 8);
                    if (++slot == kSlots) slot = 0;
                }
            }
            float4 r;
            {
                float ylo[8], yhi[8];
#pragma unroll
                for (int t = 0; t < 8; t++) { ylo[t] = o[t][0] + o[t ^ 1][1]; yhi[t] = o[t][2] + o[t ^ 1][3]; }
                r.x = ylo[0]; r.y = ylo[1]; r.z = yhi[0]; r.w = yhi[1];
#pragma unroll
                for (int d = 1; d < 4; d++) {
                    r.x += __shfl_xor_sync(0xffffffffu, ylo[2 * d], d);
                    r.y += __shfl_xor_sync(0xffffffffu, ylo[2 * d + 1], d);
                    r.z += __shfl_xor_sync(0xffffffffu, yhi[2 * d], d);
                    r.w += __shfl_xor_sync(0xffffffffu, yhi[2 * d + 1], d);
                }
            }
            if (!big && !cleared) { mbar_wait(bars + kBarClr * 8, 0); cleared = true; }
            unsigned* pp = g_part + (size_t)chunk * kRec;
            const float il = rcp(l);
            st_relaxed_v2(pp + 2 * lane, make_uint2(payload(pack_bf16(r.x * il, r.y * il)), payload(pack_bf16(r.z * il, r.w * il))));
            if (lane < 4) st_relaxed_v2(pp + 64 + 2 * lane, make_uint2(payload(m), payload(l)));
            if (big) {
                __syncwarp();
                if (lane == 0) red_release_add(&g_paircnt[pair * 8], 1u);
            }
            ph ^= 1;
        }
        if (!owner) return;

        const int h = cta >> 2, qt = cta & 3;
        mbar_wait(bars + kBarO * 8, 0);
        uint32_t af[8][4];
        const uint32_t aaddr = sb + kOffO + min(lane & 15, kB - 2) * kOPitch + hf * 16;
#pragma unroll
        for (int ks = 0; ks < 8; ks++) ldsm_x4(af[ks][0], af[ks][1], af[ks][2], af[ks][3], aaddr + ks * 32);
        const uint32_t baddr = sb + kOffW + lane * 128 + ((warp ^ (lane & 7)) << 4);
        uint32_t bw[4][16];
        auto load_piece = [&](int k) {
#pragma unroll
            for (int i = 0; i < 4; i++)
                ldsm_x4_t(bw[k][4 * i], bw[k][4 * i + 1], bw[k][4 * i + 2], bw[k][4 * i + 3], baddr + k * 16384 + i * 4096);
        };
        const unsigned* rec = g_part + (size_t)(kBigChunks + h * 32 + 4 * warp) * kRec;
        const unsigned* up = rec + hf * kRec + (lane & 15) * 4;
        asm volatile("" : "+l"(rec), "+l"(up));
        int wk = 0;
        bool merged = false;
        unsigned spins = 0;
        do {
            uint4 u0, u1;
            uint2 ml[4];
            if (!merged) {
                u0 = ld_relaxed_v4(up);
                u1 = ld_relaxed_v4(up + 2 * kRec);
#pragma unroll
                for (int i = 0; i < 4; i++) ml[i] = ld_relaxed_v2(rec + i * kRec + 64);
            }
#pragma unroll
            for (int k = 0; k < 3; k++)
                if (wk == k && __all_sync(0xffffffffu, mbar_test(bars + (kBarWo + k) * 8, 0))) {
                    load_piece(k);
                    wk = k + 1;
                }
            if (!merged) {
                const unsigned t = __vimax3_u32(
                    __vimax3_u32(__vimax3_u32(u0.x, u0.y, u0.z), __vimax3_u32(u0.w, u1.x, u1.y), max(u1.z, u1.w)),
                    __vimax3_u32(__vimax3_u32(ml[0].x, ml[0].y, ml[1].x), ml[1].y, ml[2].x),
                    __vimax3_u32(ml[2].y, ml[3].x, ml[3].y));
                if (__all_sync(0xffffffffu, t != kEmpty)) {
                    const float m = fmaxf(fmaxf(__uint_as_float(ml[0].x), __uint_as_float(ml[1].x)),
                                          fmaxf(__uint_as_float(ml[2].x), __uint_as_float(ml[3].x)));
                    float wgt[4];
#pragma unroll
                    for (int i = 0; i < 4; i++) wgt[i] = __uint_as_float(ml[i].y) * ex2(__uint_as_float(ml[i].x) - m);
                    const float f0 = hf ? wgt[1] : wgt[0], f1 = hf ? wgt[3] : wgt[2];
                    const uint2 k0 = hf ? make_uint2(u0.z, u0.w) : make_uint2(u0.x, u0.y);
                    const uint2 k1 = hf ? make_uint2(u1.z, u1.w) : make_uint2(u1.x, u1.y);
                    const uint2 e0 = hf ? make_uint2(u0.x, u0.y) : make_uint2(u0.z, u0.w);
                    const uint2 e1 = hf ? make_uint2(u1.x, u1.y) : make_uint2(u1.z, u1.w);
                    float4 v;
                    v.x = __shfl_xor_sync(0xffffffffu, f0 * bf_lo(e0.x) + f1 * bf_lo(e1.x), 16) + (f0 * bf_lo(k0.x) + f1 * bf_lo(k1.x));
                    v.y = __shfl_xor_sync(0xffffffffu, f0 * bf_hi(e0.x) + f1 * bf_hi(e1.x), 16) + (f0 * bf_hi(k0.x) + f1 * bf_hi(k1.x));
                    v.z = __shfl_xor_sync(0xffffffffu, f0 * bf_lo(e0.y) + f1 * bf_lo(e1.y), 16) + (f0 * bf_lo(k0.y) + f1 * bf_lo(k1.y));
                    v.w = __shfl_xor_sync(0xffffffffu, f0 * bf_hi(e0.y) + f1 * bf_hi(e1.y), 16) + (f0 * bf_hi(k0.y) + f1 * bf_hi(k1.y));
                    *reinterpret_cast<float4*>(smem + kOffMrg + warp * 512 + lane * 16) = v;
                    if (lane == 0)
                        *reinterpret_cast<float2*>(smem + kOffMrg + 4096 + warp * 8) = make_float2(m, (wgt[0] + wgt[1]) + (wgt[2] + wgt[3]));
                    __syncwarp();
                    if (lane == 0) mbar_arrive(bars + kBarMrg * 8);
                    merged = true;
                }
            }
            poll_tick(spins);
        } while (!merged || wk < 3);
        mbar_wait(bars + kBarO15 * 8, 0);
#pragma unroll
        for (int k = 0; k < 4; k++) {
            const uint4 ov = *reinterpret_cast<const uint4*>(smem + kOffRow + j * 64 + k * 16);
            if (g == 7) { af[2 * k][1] = ov.x; af[2 * k][3] = ov.y; af[2 * k + 1][1] = ov.z; af[2 * k + 1][3] = ov.w; }
        }
        uint2* const dst = g_mail + ((size_t)((4 * warp + qt) * 32 + h) * 32 + lane);
#pragma unroll
        for (int k = 0; k < 4; k++) {
            if (k == 3) {
                mbar_wait(bars + (kBarWo + 3) * 8, 0);
                load_piece(3);
            }
            float c[2][4];
            c[0][0] = c[0][1] = c[0][2] = c[0][3] = c[1][0] = c[1][1] = c[1][2] = c[1][3] = 0.f;
#pragma unroll
            for (int ks = 0; ks < 8; ks++)
                mma_bf16(c[ks & 1], af[ks][0], af[ks][1], af[ks][2], af[ks][3], bw[k][2 * ks], bw[k][2 * ks + 1]);
            st_relaxed_v2(dst + k * 32 * 32 * 32,
                          make_uint2(payload(pack_bf16(c[0][0] + c[1][0], c[0][1] + c[1][1])),
                                     payload(pack_bf16(c[0][2] + c[1][2], c[0][3] + c[1][3]))));
        }
        {
            const uint2* src = g_mail + ((size_t)cta * 32 + 4 * warp) * 32 + lane;
            uint2 v[4];
#pragma unroll
            for (int k = 0; k < 4; k++) v[k] = make_uint2(kEmpty, kEmpty);
            for (;;) {
#pragma unroll
                for (int k = 0; k < 4; k++)
                    if (max(v[k].x, v[k].y) == kEmpty) v[k] = ld_relaxed_v2(src + k * 32);
                const unsigned t = __vimax3_u32(__vimax3_u32(v[0].x, v[0].y, v[1].x), __vimax3_u32(v[1].y, v[2].x, v[2].y),
                                                max(v[3].x, v[3].y));
                if (t != kEmpty) break;
                poll_tick(spins);
            }
            float* red = reinterpret_cast<float*>(smem + kOffRed);
            *reinterpret_cast<float4*>(red + warp * 128 + lane * 4) =
                make_float4((bf_lo(v[0].x) + bf_lo(v[1].x)) + (bf_lo(v[2].x) + bf_lo(v[3].x)),
                            (bf_hi(v[0].x) + bf_hi(v[1].x)) + (bf_hi(v[2].x) + bf_hi(v[3].x)),
                            (bf_lo(v[0].y) + bf_lo(v[1].y)) + (bf_lo(v[2].y) + bf_lo(v[3].y)),
                            (bf_hi(v[0].y) + bf_hi(v[1].y)) + (bf_hi(v[2].y) + bf_hi(v[3].y)));
            __syncwarp();
            named_bar_sync(1, kCW * 32);
            if (tid < 64) {
                float s0 = 0.f, s1 = 0.f;
#pragma unroll
                for (int w = 0; w < kCW; w++) {
                    const float2 t = *reinterpret_cast<const float2*>(red + w * 128 + tid * 2);
                    s0 += t.x; s1 += t.y;
                }
                const int ln = tid >> 1, b = (ln >> 2) + (tid & 1) * 8;
                *reinterpret_cast<uint32_t*>(out + b * kD + qt * 256 + h * 8 + 2 * (ln & 3)) = pack_bf16(s0, s1);
                if (cta == 0 && tid == 0) g_epoch = epoch;
            }
        }
    } else if (warp == kCW) {
        if (lane == 0) {
#pragma unroll
            for (int i = 0; i < kNumBars; i++)
                mbar_init(bars + i * 8, i == kBarMrg ? kCW : (i >= kBarInfo && i < kBarEmpty ? 2 : 1));
            asm volatile("fence.mbarrier_init.release.cluster;" ::: "memory");
        }
        __syncwarp();
        named_bar_arrive(0, kThreads);
        if (lane != 0) return;
        uint64_t pol;
        asm volatile("createpolicy.fractional.L2::evict_first.b64 %0, 1.0;" : "=l"(pol));
        uint32_t fifo[kWinLast];
#pragma unroll
        for (int k = 0; k < kWinLast; k++) fifo[k] = 0;
        int win = kWin;
        auto throttle = [&](uint32_t next) {
            const uint32_t f = win == kWin ? fifo[kWinLast - kWin] : (win == kWinWo ? fifo[kWinLast - kWinWo] : fifo[0]);
            if (f) mbar_wait(f & ~1u, f & 1u);
#pragma unroll
            for (int k = 0; k + 1 < kWinLast; k++) fifo[k] = fifo[k + 1];
            fifo[kWinLast - 1] = next;
        };
        int cur = cta, nxt = 0, i = 0, slot = 0;
        uint32_t eph = 1;
        while (cur < kChunks) {
            const int w = i & (kCW - 1);
            const uint32_t ph = (uint32_t)(i >> 3) & 1u;
            desc[ph * kCW + w].x = cur; desc[ph * kCW + w].y = slot;
            mbar_arrive(bars + (kBarInfo + w) * 8);
            const bool big = cur < kBigChunks;
            if (!big) asm volatile("prefetch.tensormap [%0];" ::"l"(&wo_map) : "memory");
            if (cur >= kChunks - nctas) win = kWinLast;
            const size_t off = big ? (size_t)cur * (128 * kDh) : (size_t)(cur + kBigChunks) * (64 * kDh);
#pragma unroll
            for (int t = 0; t < 4; t++) {
                if ((t & 1) == 0 || big) {
                    const uint32_t fb = bars + (kBarFull + w * 4 + t) * 8;
                    throttle(fb | ph);
                    mbar_wait(bars + (kBarEmpty + slot) * 8, eph);
                    mbar_expect_tx(fb, kTileBytes);
                    bulk_load(sb + slot * kTileBytes, (t < 2 ? kc : vc) + off + (t & 1) * (64 * kDh), kTileBytes, fb, pol);
                    if (++slot == kSlots) { slot = 0; eph ^= 1; }
                }
                if (t == (big ? 1 : 0)) {
                    const unsigned v = atomicAdd(&g_work, 1u);
                    if (v == (unsigned)(kChunks - 1)) g_work = 0;
                    nxt = (int)v + nctas;
                }
            }
            cur = nxt;
            i++;
        }
        for (int k = 0; k < kCW; k++, i++) {
            const int w = i & (kCW - 1);
            desc[((i >> 3) & 1) * kCW + w].x = -1;
            mbar_arrive(bars + (kBarInfo + w) * 8);
        }
        if (owner) {
            win = kWinWo;
#pragma unroll 1
            for (int k = 0; k < 4; k++) {
                const uint32_t wb = bars + (kBarWo + k) * 8;
                throttle(wb);
                mbar_expect_tx(wb, 16384);
                asm volatile("cp.async.bulk.tensor.2d.shared::cluster.global.mbarrier::complete_tx::bytes.L2::cache_hint"
                             " [%0], [%1, {%3, %4}], [%2], %5;"
                             ::"r"(sb + kOffW + k * 16384), "l"(&wo_map), "r"(wb),
                               "r"((cta & 3) * 256 + k * 64), "r"((cta >> 2) * 128), "l"(pol) : "memory");
            }
        }
    } else {
        if (lane == 0) *s_epoch = ld_relaxed(&g_epoch) + 1u;
        __syncwarp();
        named_bar_sync(0, kThreads);
        const unsigned epoch = *s_epoch;
        const int h = cta >> 2;
#pragma unroll 1
        for (int b = 0; b < kB; b++) {
            if (b == kB - 4 && owner) {
                const uint4 e = make_uint4(kEmpty, kEmpty, kEmpty, kEmpty);
                uint4* inbox = reinterpret_cast<uint4*>(g_mail + (size_t)cta * 1024);
#pragma unroll 4
                for (int k = 0; k < 16; k++) __stcg(inbox + k * 32 + lane, e);
                uint4* lastp = reinterpret_cast<uint4*>(g_part + (size_t)kBigChunks * kRec);
                for (int k = cta * 32 + lane; k < kH * 32 * (kRec / 4); k += kOwners * 32) __stcg(lastp + k, e);
                __syncwarp();
                if (lane == 0) red_release_add(&g_cleared, 1u);
            }
            if (b == kB - 2) {
                if (lane == 0) {
                    unsigned spins = 0;
                    while (ld_acquire(&g_cleared) != epoch * (unsigned)kOwners) {
                        __nanosleep(500);
                        poll_tick(spins);
                    }
                    mbar_arrive(bars + kBarClr * 8);
                }
                __syncwarp();
            }
            if (!owner) continue;
            float v[4];
            if (b != kB - 1) {
                const int pair = b * kH + h;
                if (lane == 0) {
                    unsigned spins = 0;
                    while (ld_acquire(&g_paircnt[pair * 8]) != epoch * 16u) {
                        __nanosleep(400);
                        poll_tick(spins);
                    }
                }
                __syncwarp();
                const unsigned* rec = g_part + (size_t)(pair * 16) * kRec;
                uint4 u[8];
#pragma unroll
                for (int i = 0; i < 8; i++) u[i] = ld_relaxed_v4(rec + (2 * i + hf) * kRec + (lane & 15) * 4);
                const uint2 mu = ld_relaxed_v2(rec + (lane & 15) * kRec + 64);
                float m = __uint_as_float(mu.x);
#pragma unroll
                for (int d = 1; d < 16; d <<= 1) m = fmaxf(m, __shfl_xor_sync(0xffffffffu, m, d));
                const float wgt = __uint_as_float(mu.y) * ex2(__uint_as_float(mu.x) - m);
                float acc[8], l = 0.f;
#pragma unroll
                for (int k = 0; k < 8; k++) acc[k] = 0.f;
#pragma unroll
                for (int i = 0; i < 8; i++) {
                    const float f = __shfl_sync(0xffffffffu, wgt, 2 * i + hf);
                    l += f;
                    acc[0] += f * bf_lo(u[i].x); acc[1] += f * bf_hi(u[i].x);
                    acc[2] += f * bf_lo(u[i].y); acc[3] += f * bf_hi(u[i].y);
                    acc[4] += f * bf_lo(u[i].z); acc[5] += f * bf_hi(u[i].z);
                    acc[6] += f * bf_lo(u[i].w); acc[7] += f * bf_hi(u[i].w);
                }
                const float inv = rcp(l + __shfl_xor_sync(0xffffffffu, l, 16));
#pragma unroll
                for (int k = 0; k < 4; k++)
                    v[k] = ((hf ? acc[4 + k] : acc[k]) + __shfl_xor_sync(0xffffffffu, hf ? acc[k] : acc[4 + k], 16)) * inv;
            } else {
                mbar_wait(bars + kBarMrg * 8, 0);
                float2 ml[kCW];
#pragma unroll
                for (int w = 0; w < kCW; w += 2) {
                    const float4 t = *reinterpret_cast<const float4*>(smem + kOffMrg + 4096 + w * 8);
                    ml[w] = make_float2(t.x, t.y); ml[w + 1] = make_float2(t.z, t.w);
                }
                const float m = fmaxf(fmaxf(fmaxf(ml[0].x, ml[1].x), fmaxf(ml[2].x, ml[3].x)),
                                      fmaxf(fmaxf(ml[4].x, ml[5].x), fmaxf(ml[6].x, ml[7].x)));
                float l = 0.f;
                v[0] = v[1] = v[2] = v[3] = 0.f;
#pragma unroll
                for (int w = 0; w < kCW; w++) {
                    const float f = ex2(ml[w].x - m);
                    const float4 t = *reinterpret_cast<const float4*>(smem + kOffMrg + w * 512 + lane * 16);
                    l += f * ml[w].y;
                    v[0] += f * t.x; v[1] += f * t.y; v[2] += f * t.z; v[3] += f * t.w;
                }
                const float inv = rcp(l);
                v[0] *= inv; v[1] *= inv; v[2] *= inv; v[3] *= inv;
            }
            const int gw = (lane & 15) >> 1, jw = 2 * (lane & 1) + hf;
            __nv_bfloat16* orow = b != kB - 1
                ? reinterpret_cast<__nv_bfloat16*>(smem + kOffO + b * kOPitch) + 16 * jw + gw
                : reinterpret_cast<__nv_bfloat16*>(smem + kOffRow) + (gw >> 1) * 32 + jw * 4 + (gw & 1);
            const int s1 = b != kB - 1 ? 8 : 2, s2 = b != kB - 1 ? 64 : 16;
            orow[0] = __float2bfloat16(v[0]);
            orow[s1] = __float2bfloat16(v[1]);
            orow[s2] = __float2bfloat16(v[2]);
            orow[s1 + s2] = __float2bfloat16(v[3]);
            if (b >= kB - 2) {
                __syncwarp();
                if (lane == 0) mbar_arrive(bars + (b == kB - 2 ? kBarO : kBarO15) * 8);
            }
        }
    }
}

__device__ float g_fb_q[kB * kHD], g_fb_o[kB * kHD];

__global__ void fb_q_kernel(const __nv_bfloat16* __restrict__ x, const __nv_bfloat16* __restrict__ wq) {
    const int n = blockIdx.x * 256 + threadIdx.x, b = blockIdx.y;
    float a = 0.f;
    for (int k = 0; k < kD; k++) a += __bfloat162float(x[b * kD + k]) * __bfloat162float(wq[(size_t)k * kHD + n]);
    g_fb_q[b * kHD + n] = __bfloat162float(__float2bfloat16(a));
}
__global__ void fb_attn_kernel(const __nv_bfloat16* __restrict__ kc, const __nv_bfloat16* __restrict__ vc) {
    __shared__ float sc[kSk], qs[kDh], red[kDh];
    const int pair = blockIdx.x, t = threadIdx.x;
    const __nv_bfloat16* kp = kc + (size_t)pair * kSk * kDh;
    const __nv_bfloat16* vp = vc + (size_t)pair * kSk * kDh;
    qs[t] = g_fb_q[pair * kDh + t];
    __syncthreads();
    float m = -INFINITY;
    for (int i = t; i < kSk; i += kDh) {
        float a = 0.f;
        for (int d = 0; d < kDh; d++) a += qs[d] * __bfloat162float(kp[i * kDh + d]);
        sc[i] = __bfloat162float(__float2bfloat16(__bfloat162float(__float2bfloat16(a)) * 0.08838834764831845f));
        m = fmaxf(m, sc[i]);
    }
    red[t] = m;
    __syncthreads();
    for (int i = 0; i < kDh; i++) m = fmaxf(m, red[i]);
    __syncthreads();
    float l = 0.f;
    for (int i = t; i < kSk; i += kDh) { sc[i] = __expf(sc[i] - m); l += sc[i]; }
    red[t] = l;
    __syncthreads();
    l = 0.f;
    for (int i = 0; i < kDh; i++) l += red[i];
    float a = 0.f;
    for (int i = 0; i < kSk; i++) a += sc[i] * __bfloat162float(vp[i * kDh + t]);
    g_fb_o[pair * kDh + t] = __bfloat162float(__float2bfloat16(a / l));
}
__global__ void fb_out_kernel(const __nv_bfloat16* __restrict__ wo, __nv_bfloat16* __restrict__ out) {
    const int n = blockIdx.x * 256 + threadIdx.x, b = blockIdx.y;
    float a = 0.f;
    for (int k = 0; k < kHD; k++) a += g_fb_o[b * kHD + k] * __bfloat162float(wo[(size_t)k * kD + n]);
    out[b * kD + n] = __float2bfloat16(a);
}

}

extern "C" void kernel_launch(void* const* d_in, const int* in_sizes, int n_in, void* d_out, int out_size) {
    (void)in_sizes; (void)n_in; (void)out_size;
    const __nv_bfloat16* x = (const __nv_bfloat16*)d_in[0];
    const __nv_bfloat16* kc = (const __nv_bfloat16*)d_in[1];
    const __nv_bfloat16* vc = (const __nv_bfloat16*)d_in[2];
    const __nv_bfloat16* wq = (const __nv_bfloat16*)d_in[3];
    const __nv_bfloat16* wo = (const __nv_bfloat16*)d_in[4];
    __nv_bfloat16* out = (__nv_bfloat16*)d_out;

    static int grid = -1;
    static CUtensorMap wo_map;
    static const void* wo_seen = nullptr;
    if (grid < 0) {
        int dev = 0, sms = 0, occ = 0;
        cudaGetDevice(&dev);
        cudaDeviceGetAttribute(&sms, cudaDevAttrMultiProcessorCount, dev);
        if (cudaFuncSetAttribute(mha_decode_kernel, cudaFuncAttributeMaxDynamicSharedMemorySize, kSmemBytes) == cudaSuccess)
            cudaOccupancyMaxActiveBlocksPerMultiprocessor(&occ, mha_decode_kernel, kThreads, kSmemBytes);
        (void)cudaGetLastError();
        grid = (occ >= 1 && sms >= kOwners) ? sms : 0;
    }
    if (grid > 0 && wo_seen != (const void*)wo) {
        typedef CUresult (*EncodeFn)(CUtensorMap*, CUtensorMapDataType, cuuint32_t, void*, const cuuint64_t*,
                                     const cuuint64_t*, const cuuint32_t*, const cuuint32_t*, CUtensorMapInterleave,
                                     CUtensorMapSwizzle, CUtensorMapL2promotion, CUtensorMapFloatOOBfill);
        void* fn = nullptr;
        cudaDriverEntryPointQueryResult qr;
        cudaGetDriverEntryPoint("cuTensorMapEncodeTiled", &fn, cudaEnableDefault, &qr);
        const cuuint64_t dims[2] = {(cuuint64_t)kD, (cuuint64_t)kHD}, strides[1] = {(cuuint64_t)kD * 2};
        const cuuint32_t box[2] = {64, 128}, estr[2] = {1, 1};
        if (fn == nullptr ||
            ((EncodeFn)fn)(&wo_map, CU_TENSOR_MAP_DATA_TYPE_BFLOAT16, 2, (void*)wo, dims, strides, box, estr,
                           CU_TENSOR_MAP_INTERLEAVE_NONE, CU_TENSOR_MAP_SWIZZLE_128B, CU_TENSOR_MAP_L2_PROMOTION_L2_128B,
                           CU_TENSOR_MAP_FLOAT_OOB_FILL_NONE) != CUDA_SUCCESS)
            grid = 0;
        wo_seen = (const void*)wo;
    }
    if (grid > 0) {
        mha_decode_kernel<<<grid, kThreads, kSmemBytes>>>(x, kc, vc, wq, wo_map, out);
    } else {
        fb_q_kernel<<<dim3(kHD / 256, kB), 256>>>(x, wq);
        fb_attn_kernel<<<kB * kH, kDh>>>(kc, vc);
        fb_out_kernel<<<dim3(kD / 256, kB), 256>>>(wo, out);
    }
}
```
